```python
import torch

def _softmax(x, axis=-1):
    return torch.softmax(x, dim=axis)
def _gelu(x):
    return torch.nn.functional.gelu(x, approximate="tanh")
def _silu(x):
    return torch.nn.functional.silu(x)
def _sigmoid(x):
    return torch.sigmoid(x)
def _layernorm(x, axis=-1, eps=1e-5):
    m = x.mean(dim=axis, keepdim=True)
    v = x.var(dim=axis, keepdim=True, unbiased=False)
    return (x - m) / torch.sqrt(v + eps)
def _scatter_add(tgt, idx, src, axis=0):
    return tgt.clone().index_add_(axis, idx, src)
def _segment_sum(src, seg, n):
    out = torch.zeros((n,) + src.shape[1:], dtype=src.dtype)
    return out.index_add_(0, seg, src)
def _pad(x, pw):
    flat = tuple(v for pair in reversed(pw) for v in pair)
    return torch.nn.functional.pad(x, flat)

kernel_name = 'standalone__glu_gated_reglu__prompt'

def setup_inputs():

    _w = (lambda a: (lambda t: t.to(torch.bfloat16) if t.is_floating_point() else t)(torch.as_tensor(a)))
    B, S, D, F = 1, 2048, 576, 4608
    return {
        "x": _w((lambda *s: torch.randn(*s, dtype=torch.bfloat16) * 0.05)(B, S, D)),
        "W_gate": _w((lambda *s: torch.randn(*s, dtype=torch.bfloat16) * 0.05)(D, F) * (2.0 / D) ** 0.5),
        "W_up": _w((lambda *s: torch.randn(*s, dtype=torch.bfloat16) * 0.05)(D, F) * (2.0 / D) ** 0.5),
        "W_down": _w((lambda *s: torch.randn(*s, dtype=torch.bfloat16) * 0.05)(F, D) * (1.0 / F) ** 0.5),
    }

def reference(x, W_gate, W_up, W_down):
    gate = torch.einsum("bsd,df->bsf", x, W_gate)
    up = torch.einsum("bsd,df->bsf", x, W_up)
    gate = gate * (lambda x, dt: x.to(dt))(gate > 0, gate.dtype)
    h = gate * up
    return torch.einsum("bsf,fd->bsd", h, W_down)
```

```cpp
#include <cuda_runtime.h>
#include <cuda_bf16.h>
#include <cuda.h>
#include <stdint.h>

namespace {

constexpr int S_ = 2048, D_ = 576, F_ = 4608;
constexpr int NGRID = 132;
constexpr int W_STAGES = 5;
constexpr int P2_STAGES = 5;
constexpr int FLOAT_LEVELS = 2;
constexpr int SKEW = 4;
constexpr uint32_t X_BYTES = 9 * 16384;
constexpr uint32_t W_STAGE_BYTES = 16384;
constexpr uint32_t P2_A_BYTES = 16384, P2_B_BYTES = 24576, P2_STAGE_BYTES = P2_A_BYTES + P2_B_BYTES;
constexpr uint32_t OFF_W = X_BYTES;
constexpr uint32_t OFF_STG = P2_STAGES * P2_STAGE_BYTES;
constexpr uint32_t OFF_BAR = X_BYTES + W_STAGES * W_STAGE_BYTES;
constexpr uint32_t SMEM_BYTES = OFF_BAR + 1024 + 1024;
__device__ __forceinline__ uint32_t p2_slot(uint32_t s) { return (s == 2 ? 4u : (s > 2 ? s - 1 : s)) * P2_STAGE_BYTES; }

struct CtaSched { uint8_t m, j, nseg, pad; uint8_t seg_m[4], seg_n[4], seg_cnt[4]; uint8_t kb[64]; };
__device__ const __align__(16) CtaSched g_sched[NGRID] = {
{0,0,1,0,{0,0,0,0},{0,0,0,0},{26,0,0,0},{0,9,18,1,10,19,2,11,20,3,12,21,4,13,22,5,14,23,6,15,24,7,16,25,8,17,0,0,0,0,0,0,0,0,0,0,0,0,0,0,0,0,0,0,0,0,0,0,0,0,0,0,0,0,0,0,0,0,0,0,0,0,0,0}},
{1,0,1,0,{1,0,0,0},{0,0,0,0},{26,0,0,0},{0,9,18,1,10,19,2,11,20,3,12,21,4,13,22,5,14,23,6,15,24,7,16,25,8,17,0,0,0,0,0,0,0,0,0,0,0,0,0,0,0,0,0,0,0,0,0,0,0,0,0,0,0,0,0,0,0,0,0,0,0,0,0,0}},
{2,0,1,0,{2,0,0,0},{0,0,0,0},{26,0,0,0},{0,9,18,1,10,19,2,11,20,3,12,21,4,13,22,5,14,23,6,15,24,7,16,25,8,17,0,0,0,0,0,0,0,0,0,0,0,0,0,0,0,0,0,0,0,0,0,0,0,0,0,0,0,0,0,0,0,0,0,0,0,0,0,0}},
{3,0,1,0,{3,0,0,0},{0,0,0,0},{26,0,0,0},{0,9,18,1,10,19,2,11,20,3,12,21,4,13,22,5,14,23,6,15,24,7,16,25,8,17,0,0,0,0,0,0,0,0,0,0,0,0,0,0,0,0,0,0,0,0,0,0,0,0,0,0,0,0,0,0,0,0,0,0,0,0,0,0}},
{0,1,1,0,{0,0,0,0},{0,0,0,0},{26,0,0,0},{27,36,45,28,37,46,29,38,47,30,39,48,31,40,49,32,41,50,33,42,51,34,43,26,35,44,0,0,0,0,0,0,0,0,0,0,0,0,0,0,0,0,0,0,0,0,0,0,0,0,0,0,0,0,0,0,0,0,0,0,0,0,0,0}},
{1,1,1,0,{1,0,0,0},{0,0,0,0},{26,0,0,0},{27,36,45,28,37,46,29,38,47,30,39,48,31,40,49,32,41,50,33,42,51,34,43,26,35,44,0,0,0,0,0,0,0,0,0,0,0,0,0,0,0,0,0,0,0,0,0,0,0,0,0,0,0,0,0,0,0,0,0,0,0,0,0,0}},
{2,1,1,0,{2,0,0,0},{0,0,0,0},{26,0,0,0},{27,36,45,28,37,46,29,38,47,30,39,48,31,40,49,32,41,50,33,42,51,34,43,26,35,44,0,0,0,0,0,0,0,0,0,0,0,0,0,0,0,0,0,0,0,0,0,0,0,0,0,0,0,0,0,0,0,0,0,0,0,0,0,0}},
{3,1,1,0,{3,0,0,0},{0,0,0,0},{26,0,0,0},{27,36,45,28,37,46,29,38,47,30,39,48,31,40,49,32,41,50,33,42,51,34,43,26,35,44,0,0,0,0,0,0,0,0,0,0,0,0,0,0,0,0,0,0,0,0,0,0,0,0,0,0,0,0,0,0,0,0,0,0,0,0,0,0}},
{0,2,2,0,{0,0,0,0},{0,1,0,0},{20,3,0,0},{54,63,55,64,56,65,57,66,58,67,59,68,60,69,52,61,70,53,62,71,2,3,4,0,0,0,0,0,0,0,0,0,0,0,0,0,0,0,0,0,0,0,0,0,0,0,0,0,0,0,0,0,0,0,0,0,0,0,0,0,0,0,0,0}},
{1,2,2,0,{1,1,0,0},{0,1,0,0},{20,3,0,0},{54,63,55,64,56,65,57,66,58,67,59,68,60,69,52,61,70,53,62,71,2,3,4,0,0,0,0,0,0,0,0,0,0,0,0,0,0,0,0,0,0,0,0,0,0,0,0,0,0,0,0,0,0,0,0,0,0,0,0,0,0,0,0,0}},
{2,2,2,0,{2,2,0,0},{0,1,0,0},{20,3,0,0},{54,63,55,64,56,65,57,66,58,67,59,68,60,69,52,61,70,53,62,71,2,3,4,0,0,0,0,0,0,0,0,0,0,0,0,0,0,0,0,0,0,0,0,0,0,0,0,0,0,0,0,0,0,0,0,0,0,0,0,0,0,0,0,0}},
{3,2,2,0,{3,3,0,0},{0,1,0,0},{20,3,0,0},{54,63,55,64,56,65,57,66,58,67,59,68,60,69,52,61,70,53,62,71,2,3,4,0,0,0,0,0,0,0,0,0,0,0,0,0,0,0,0,0,0,0,0,0,0,0,0,0,0,0,0,0,0,0,0,0,0,0,0,0,0,0,0,0}},
{0,3,1,0,{0,0,0,0},{1,0,0,0},{26,0,0,0},{11,20,29,38,12,21,30,13,22,31,5,14,23,32,6,15,24,33,7,16,25,34,8,17,26,35,0,0,0,0,0,0,0,0,0,0,0,0,0,0,0,0,0,0,0,0,0,0,0,0,0,0,0,0,0,0,0,0,0,0,0,0,0,0}},
{1,3,1,0,{1,0,0,0},{1,0,0,0},{26,0,0,0},{11,20,29,38,12,21,30,13,22,31,5,14,23,32,6,15,24,33,7,16,25,34,8,17,26,35,0,0,0,0,0,0,0,0,0,0,0,0,0,0,0,0,0,0,0,0,0,0,0,0,0,0,0,0,0,0,0,0,0,0,0,0,0,0}},
{2,3,1,0,{2,0,0,0},{1,0,0,0},{26,0,0,0},{11,20,29,38,12,21,30,13,22,31,5,14,23,32,6,15,24,33,7,16,25,34,8,17,26,35,0,0,0,0,0,0,0,0,0,0,0,0,0,0,0,0,0,0,0,0,0,0,0,0,0,0,0,0,0,0,0,0,0,0,0,0,0,0}},
{3,3,1,0,{3,0,0,0},{1,0,0,0},{26,0,0,0},{11,20,29,38,12,21,30,13,22,31,5,14,23,32,6,15,24,33,7,16,25,34,8,17,26,35,0,0,0,0,0,0,0,0,0,0,0,0,0,0,0,0,0,0,0,0,0,0,0,0,0,0,0,0,0,0,0,0,0,0,0,0,0,0}},
{0,4,1,0,{0,0,0,0},{1,0,0,0},{26,0,0,0},{55,64,47,56,65,39,48,57,66,40,49,58,67,41,50,59,68,42,51,60,43,52,61,44,53,62,0,0,0,0,0,0,0,0,0,0,0,0,0,0,0,0,0,0,0,0,0,0,0,0,0,0,0,0,0,0,0,0,0,0,0,0,0,0}},
{1,4,1,0,{1,0,0,0},{1,0,0,0},{26,0,0,0},{55,64,47,56,65,39,48,57,66,40,49,58,67,41,50,59,68,42,51,60,43,52,61,44,53,62,0,0,0,0,0,0,0,0,0,0,0,0,0,0,0,0,0,0,0,0,0,0,0,0,0,0,0,0,0,0,0,0,0,0,0,0,0,0}},
{2,4,1,0,{2,0,0,0},{1,0,0,0},{26,0,0,0},{55,64,47,56,65,39,48,57,66,40,49,58,67,41,50,59,68,42,51,60,43,52,61,44,53,62,0,0,0,0,0,0,0,0,0,0,0,0,0,0,0,0,0,0,0,0,0,0,0,0,0,0,0,0,0,0,0,0,0,0,0,0,0,0}},
{3,4,1,0,{3,0,0,0},{1,0,0,0},{26,0,0,0},{55,64,47,56,65,39,48,57,66,40,49,58,67,41,50,59,68,42,51,60,43,52,61,44,53,62,0,0,0,0,0,0,0,0,0,0,0,0,0,0,0,0,0,0,0,0,0,0,0,0,0,0,0,0,0,0,0,0,0,0,0,0,0,0}},
{0,5,2,0,{0,0,0,0},{2,1,0,0},{20,3,0,0},{0,9,18,1,10,19,2,11,3,12,4,13,5,14,6,15,7,16,8,17,69,70,71,0,0,0,0,0,0,0,0,0,0,0,0,0,0,0,0,0,0,0,0,0,0,0,0,0,0,0,0,0,0,0,0,0,0,0,0,0,0,0,0,0}},
{1,5,2,0,{1,1,0,0},{2,1,0,0},{20,3,0,0},{0,9,18,1,10,19,2,11,3,12,4,13,5,14,6,15,7,16,8,17,69,70,71,0,0,0,0,0,0,0,0,0,0,0,0,0,0,0,0,0,0,0,0,0,0,0,0,0,0,0,0,0,0,0,0,0,0,0,0,0,0,0,0,0}},
{2,5,2,0,{2,2,0,0},{2,1,0,0},{20,3,0,0},{0,9,18,1,10,19,2,11,3,12,4,13,5,14,6,15,7,16,8,17,69,70,71,0,0,0,0,0,0,0,0,0,0,0,0,0,0,0,0,0,0,0,0,0,0,0,0,0,0,0,0,0,0,0,0,0,0,0,0,0,0,0,0,0}},
{3,5,2,0,{3,3,0,0},{2,1,0,0},{20,3,0,0},{0,9,18,1,10,19,2,11,3,12,4,13,5,14,6,15,7,16,8,17,69,70,71,0,0,0,0,0,0,0,0,0,0,0,0,0,0,0,0,0,0,0,0,0,0,0,0,0,0,0,0,0,0,0,0,0,0,0,0,0,0,0,0,0}},
{255,255,4,0,{0,1,2,3},{1,1,1,1},{14,14,14,14},{0,9,18,27,36,45,54,63,1,10,19,28,37,46,0,9,18,27,36,45,54,63,1,10,19,28,37,46,0,9,18,27,36,45,54,63,1,10,19,28,37,46,0,9,18,27,36,45,54,63,1,10,19,28,37,46,0,0,0,0,0,0,0,0}},
{255,255,4,0,{4,5,6,7},{1,1,1,1},{14,14,14,14},{0,9,18,27,36,45,54,63,1,10,19,28,37,46,0,9,18,27,36,45,54,63,1,10,19,28,37,46,0,9,18,27,36,45,54,63,1,10,19,28,37,46,0,9,18,27,36,45,54,63,1,10,19,28,37,46,0,0,0,0,0,0,0,0}},
{0,6,1,0,{0,0,0,0},{2,0,0,0},{26,0,0,0},{27,36,45,28,37,20,29,38,21,30,39,22,31,40,23,32,41,24,33,42,25,34,43,26,35,44,0,0,0,0,0,0,0,0,0,0,0,0,0,0,0,0,0,0,0,0,0,0,0,0,0,0,0,0,0,0,0,0,0,0,0,0,0,0}},
{1,6,1,0,{1,0,0,0},{2,0,0,0},{26,0,0,0},{27,36,45,28,37,20,29,38,21,30,39,22,31,40,23,32,41,24,33,42,25,34,43,26,35,44,0,0,0,0,0,0,0,0,0,0,0,0,0,0,0,0,0,0,0,0,0,0,0,0,0,0,0,0,0,0,0,0,0,0,0,0,0,0}},
{2,6,1,0,{2,0,0,0},{2,0,0,0},{26,0,0,0},{27,36,45,28,37,20,29,38,21,30,39,22,31,40,23,32,41,24,33,42,25,34,43,26,35,44,0,0,0,0,0,0,0,0,0,0,0,0,0,0,0,0,0,0,0,0,0,0,0,0,0,0,0,0,0,0,0,0,0,0,0,0,0,0}},
{3,6,1,0,{3,0,0,0},{2,0,0,0},{26,0,0,0},{27,36,45,28,37,20,29,38,21,30,39,22,31,40,23,32,41,24,33,42,25,34,43,26,35,44,0,0,0,0,0,0,0,0,0,0,0,0,0,0,0,0,0,0,0,0,0,0,0,0,0,0,0,0,0,0,0,0,0,0,0,0,0,0}},
{0,7,1,0,{0,0,0,0},{2,0,0,0},{26,0,0,0},{54,63,46,55,64,47,56,65,48,57,66,49,58,67,50,59,68,51,60,69,52,61,70,53,62,71,0,0,0,0,0,0,0,0,0,0,0,0,0,0,0,0,0,0,0,0,0,0,0,0,0,0,0,0,0,0,0,0,0,0,0,0,0,0}},
{1,7,1,0,{1,0,0,0},{2,0,0,0},{26,0,0,0},{54,63,46,55,64,47,56,65,48,57,66,49,58,67,50,59,68,51,60,69,52,61,70,53,62,71,0,0,0,0,0,0,0,0,0,0,0,0,0,0,0,0,0,0,0,0,0,0,0,0,0,0,0,0,0,0,0,0,0,0,0,0,0,0}},
{2,7,1,0,{2,0,0,0},{2,0,0,0},{26,0,0,0},{54,63,46,55,64,47,56,65,48,57,66,49,58,67,50,59,68,51,60,69,52,61,70,53,62,71,0,0,0,0,0,0,0,0,0,0,0,0,0,0,0,0,0,0,0,0,0,0,0,0,0,0,0,0,0,0,0,0,0,0,0,0,0,0}},
{3,7,1,0,{3,0,0,0},{2,0,0,0},{26,0,0,0},{54,63,46,55,64,47,56,65,48,57,66,49,58,67,50,59,68,51,60,69,52,61,70,53,62,71,0,0,0,0,0,0,0,0,0,0,0,0,0,0,0,0,0,0,0,0,0,0,0,0,0,0,0,0,0,0,0,0,0,0,0,0,0,0}},
{4,0,1,0,{4,0,0,0},{0,0,0,0},{26,0,0,0},{0,9,18,1,10,19,2,11,20,3,12,21,4,13,22,5,14,23,6,15,24,7,16,25,8,17,0,0,0,0,0,0,0,0,0,0,0,0,0,0,0,0,0,0,0,0,0,0,0,0,0,0,0,0,0,0,0,0,0,0,0,0,0,0}},
{5,0,1,0,{5,0,0,0},{0,0,0,0},{26,0,0,0},{0,9,18,1,10,19,2,11,20,3,12,21,4,13,22,5,14,23,6,15,24,7,16,25,8,17,0,0,0,0,0,0,0,0,0,0,0,0,0,0,0,0,0,0,0,0,0,0,0,0,0,0,0,0,0,0,0,0,0,0,0,0,0,0}},
{6,0,1,0,{6,0,0,0},{0,0,0,0},{26,0,0,0},{0,9,18,1,10,19,2,11,20,3,12,21,4,13,22,5,14,23,6,15,24,7,16,25,8,17,0,0,0,0,0,0,0,0,0,0,0,0,0,0,0,0,0,0,0,0,0,0,0,0,0,0,0,0,0,0,0,0,0,0,0,0,0,0}},
{7,0,1,0,{7,0,0,0},{0,0,0,0},{26,0,0,0},{0,9,18,1,10,19,2,11,20,3,12,21,4,13,22,5,14,23,6,15,24,7,16,25,8,17,0,0,0,0,0,0,0,0,0,0,0,0,0,0,0,0,0,0,0,0,0,0,0,0,0,0,0,0,0,0,0,0,0,0,0,0,0,0}},
{4,1,1,0,{4,0,0,0},{0,0,0,0},{26,0,0,0},{27,36,45,28,37,46,29,38,47,30,39,48,31,40,49,32,41,50,33,42,51,34,43,26,35,44,0,0,0,0,0,0,0,0,0,0,0,0,0,0,0,0,0,0,0,0,0,0,0,0,0,0,0,0,0,0,0,0,0,0,0,0,0,0}},
{5,1,1,0,{5,0,0,0},{0,0,0,0},{26,0,0,0},{27,36,45,28,37,46,29,38,47,30,39,48,31,40,49,32,41,50,33,42,51,34,43,26,35,44,0,0,0,0,0,0,0,0,0,0,0,0,0,0,0,0,0,0,0,0,0,0,0,0,0,0,0,0,0,0,0,0,0,0,0,0,0,0}},
{6,1,1,0,{6,0,0,0},{0,0,0,0},{26,0,0,0},{27,36,45,28,37,46,29,38,47,30,39,48,31,40,49,32,41,50,33,42,51,34,43,26,35,44,0,0,0,0,0,0,0,0,0,0,0,0,0,0,0,0,0,0,0,0,0,0,0,0,0,0,0,0,0,0,0,0,0,0,0,0,0,0}},
{7,1,1,0,{7,0,0,0},{0,0,0,0},{26,0,0,0},{27,36,45,28,37,46,29,38,47,30,39,48,31,40,49,32,41,50,33,42,51,34,43,26,35,44,0,0,0,0,0,0,0,0,0,0,0,0,0,0,0,0,0,0,0,0,0,0,0,0,0,0,0,0,0,0,0,0,0,0,0,0,0,0}},
{4,2,2,0,{4,4,0,0},{0,1,0,0},{20,3,0,0},{54,63,55,64,56,65,57,66,58,67,59,68,60,69,52,61,70,53,62,71,2,3,4,0,0,0,0,0,0,0,0,0,0,0,0,0,0,0,0,0,0,0,0,0,0,0,0,0,0,0,0,0,0,0,0,0,0,0,0,0,0,0,0,0}},
{5,2,2,0,{5,5,0,0},{0,1,0,0},{20,3,0,0},{54,63,55,64,56,65,57,66,58,67,59,68,60,69,52,61,70,53,62,71,2,3,4,0,0,0,0,0,0,0,0,0,0,0,0,0,0,0,0,0,0,0,0,0,0,0,0,0,0,0,0,0,0,0,0,0,0,0,0,0,0,0,0,0}},
{6,2,2,0,{6,6,0,0},{0,1,0,0},{20,3,0,0},{54,63,55,64,56,65,57,66,58,67,59,68,60,69,52,61,70,53,62,71,2,3,4,0,0,0,0,0,0,0,0,0,0,0,0,0,0,0,0,0,0,0,0,0,0,0,0,0,0,0,0,0,0,0,0,0,0,0,0,0,0,0,0,0}},
{7,2,2,0,{7,7,0,0},{0,1,0,0},{20,3,0,0},{54,63,55,64,56,65,57,66,58,67,59,68,60,69,52,61,70,53,62,71,2,3,4,0,0,0,0,0,0,0,0,0,0,0,0,0,0,0,0,0,0,0,0,0,0,0,0,0,0,0,0,0,0,0,0,0,0,0,0,0,0,0,0,0}},
{4,3,1,0,{4,0,0,0},{1,0,0,0},{26,0,0,0},{11,20,29,38,12,21,30,13,22,31,5,14,23,32,6,15,24,33,7,16,25,34,8,17,26,35,0,0,0,0,0,0,0,0,0,0,0,0,0,0,0,0,0,0,0,0,0,0,0,0,0,0,0,0,0,0,0,0,0,0,0,0,0,0}},
{5,3,1,0,{5,0,0,0},{1,0,0,0},{26,0,0,0},{11,20,29,38,12,21,30,13,22,31,5,14,23,32,6,15,24,33,7,16,25,34,8,17,26,35,0,0,0,0,0,0,0,0,0,0,0,0,0,0,0,0,0,0,0,0,0,0,0,0,0,0,0,0,0,0,0,0,0,0,0,0,0,0}},
{6,3,1,0,{6,0,0,0},{1,0,0,0},{26,0,0,0},{11,20,29,38,12,21,30,13,22,31,5,14,23,32,6,15,24,33,7,16,25,34,8,17,26,35,0,0,0,0,0,0,0,0,0,0,0,0,0,0,0,0,0,0,0,0,0,0,0,0,0,0,0,0,0,0,0,0,0,0,0,0,0,0}},
{7,3,1,0,{7,0,0,0},{1,0,0,0},{26,0,0,0},{11,20,29,38,12,21,30,13,22,31,5,14,23,32,6,15,24,33,7,16,25,34,8,17,26,35,0,0,0,0,0,0,0,0,0,0,0,0,0,0,0,0,0,0,0,0,0,0,0,0,0,0,0,0,0,0,0,0,0,0,0,0,0,0}},
{4,4,1,0,{4,0,0,0},{1,0,0,0},{26,0,0,0},{55,64,47,56,65,39,48,57,66,40,49,58,67,41,50,59,68,42,51,60,43,52,61,44,53,62,0,0,0,0,0,0,0,0,0,0,0,0,0,0,0,0,0,0,0,0,0,0,0,0,0,0,0,0,0,0,0,0,0,0,0,0,0,0}},
{5,4,1,0,{5,0,0,0},{1,0,0,0},{26,0,0,0},{55,64,47,56,65,39,48,57,66,40,49,58,67,41,50,59,68,42,51,60,43,52,61,44,53,62,0,0,0,0,0,0,0,0,0,0,0,0,0,0,0,0,0,0,0,0,0,0,0,0,0,0,0,0,0,0,0,0,0,0,0,0,0,0}},
{6,4,1,0,{6,0,0,0},{1,0,0,0},{26,0,0,0},{55,64,47,56,65,39,48,57,66,40,49,58,67,41,50,59,68,42,51,60,43,52,61,44,53,62,0,0,0,0,0,0,0,0,0,0,0,0,0,0,0,0,0,0,0,0,0,0,0,0,0,0,0,0,0,0,0,0,0,0,0,0,0,0}},
{7,4,1,0,{7,0,0,0},{1,0,0,0},{26,0,0,0},{55,64,47,56,65,39,48,57,66,40,49,58,67,41,50,59,68,42,51,60,43,52,61,44,53,62,0,0,0,0,0,0,0,0,0,0,0,0,0,0,0,0,0,0,0,0,0,0,0,0,0,0,0,0,0,0,0,0,0,0,0,0,0,0}},
{4,5,2,0,{4,4,0,0},{2,1,0,0},{20,3,0,0},{0,9,18,1,10,19,2,11,3,12,4,13,5,14,6,15,7,16,8,17,69,70,71,0,0,0,0,0,0,0,0,0,0,0,0,0,0,0,0,0,0,0,0,0,0,0,0,0,0,0,0,0,0,0,0,0,0,0,0,0,0,0,0,0}},
{5,5,2,0,{5,5,0,0},{2,1,0,0},{20,3,0,0},{0,9,18,1,10,19,2,11,3,12,4,13,5,14,6,15,7,16,8,17,69,70,71,0,0,0,0,0,0,0,0,0,0,0,0,0,0,0,0,0,0,0,0,0,0,0,0,0,0,0,0,0,0,0,0,0,0,0,0,0,0,0,0,0}},
{6,5,2,0,{6,6,0,0},{2,1,0,0},{20,3,0,0},{0,9,18,1,10,19,2,11,3,12,4,13,5,14,6,15,7,16,8,17,69,70,71,0,0,0,0,0,0,0,0,0,0,0,0,0,0,0,0,0,0,0,0,0,0,0,0,0,0,0,0,0,0,0,0,0,0,0,0,0,0,0,0,0}},
{7,5,2,0,{7,7,0,0},{2,1,0,0},{20,3,0,0},{0,9,18,1,10,19,2,11,3,12,4,13,5,14,6,15,7,16,8,17,69,70,71,0,0,0,0,0,0,0,0,0,0,0,0,0,0,0,0,0,0,0,0,0,0,0,0,0,0,0,0,0,0,0,0,0,0,0,0,0,0,0,0,0}},
{4,6,1,0,{4,0,0,0},{2,0,0,0},{26,0,0,0},{27,36,45,28,37,20,29,38,21,30,39,22,31,40,23,32,41,24,33,42,25,34,43,26,35,44,0,0,0,0,0,0,0,0,0,0,0,0,0,0,0,0,0,0,0,0,0,0,0,0,0,0,0,0,0,0,0,0,0,0,0,0,0,0}},
{5,6,1,0,{5,0,0,0},{2,0,0,0},{26,0,0,0},{27,36,45,28,37,20,29,38,21,30,39,22,31,40,23,32,41,24,33,42,25,34,43,26,35,44,0,0,0,0,0,0,0,0,0,0,0,0,0,0,0,0,0,0,0,0,0,0,0,0,0,0,0,0,0,0,0,0,0,0,0,0,0,0}},
{6,6,1,0,{6,0,0,0},{2,0,0,0},{26,0,0,0},{27,36,45,28,37,20,29,38,21,30,39,22,31,40,23,32,41,24,33,42,25,34,43,26,35,44,0,0,0,0,0,0,0,0,0,0,0,0,0,0,0,0,0,0,0,0,0,0,0,0,0,0,0,0,0,0,0,0,0,0,0,0,0,0}},
{7,6,1,0,{7,0,0,0},{2,0,0,0},{26,0,0,0},{27,36,45,28,37,20,29,38,21,30,39,22,31,40,23,32,41,24,33,42,25,34,43,26,35,44,0,0,0,0,0,0,0,0,0,0,0,0,0,0,0,0,0,0,0,0,0,0,0,0,0,0,0,0,0,0,0,0,0,0,0,0,0,0}},
{4,7,1,0,{4,0,0,0},{2,0,0,0},{26,0,0,0},{54,63,46,55,64,47,56,65,48,57,66,49,58,67,50,59,68,51,60,69,52,61,70,53,62,71,0,0,0,0,0,0,0,0,0,0,0,0,0,0,0,0,0,0,0,0,0,0,0,0,0,0,0,0,0,0,0,0,0,0,0,0,0,0}},
{5,7,1,0,{5,0,0,0},{2,0,0,0},{26,0,0,0},{54,63,46,55,64,47,56,65,48,57,66,49,58,67,50,59,68,51,60,69,52,61,70,53,62,71,0,0,0,0,0,0,0,0,0,0,0,0,0,0,0,0,0,0,0,0,0,0,0,0,0,0,0,0,0,0,0,0,0,0,0,0,0,0}},
{6,7,1,0,{6,0,0,0},{2,0,0,0},{26,0,0,0},{54,63,46,55,64,47,56,65,48,57,66,49,58,67,50,59,68,51,60,69,52,61,70,53,62,71,0,0,0,0,0,0,0,0,0,0,0,0,0,0,0,0,0,0,0,0,0,0,0,0,0,0,0,0,0,0,0,0,0,0,0,0,0,0}},
{7,7,1,0,{7,0,0,0},{2,0,0,0},{26,0,0,0},{54,63,46,55,64,47,56,65,48,57,66,49,58,67,50,59,68,51,60,69,52,61,70,53,62,71,0,0,0,0,0,0,0,0,0,0,0,0,0,0,0,0,0,0,0,0,0,0,0,0,0,0,0,0,0,0,0,0,0,0,0,0,0,0}},
{8,0,1,0,{8,0,0,0},{0,0,0,0},{26,0,0,0},{0,9,18,1,10,19,2,11,20,3,12,21,4,13,22,5,14,23,6,15,24,7,16,25,8,17,0,0,0,0,0,0,0,0,0,0,0,0,0,0,0,0,0,0,0,0,0,0,0,0,0,0,0,0,0,0,0,0,0,0,0,0,0,0}},
{9,0,1,0,{9,0,0,0},{0,0,0,0},{26,0,0,0},{0,9,18,1,10,19,2,11,20,3,12,21,4,13,22,5,14,23,6,15,24,7,16,25,8,17,0,0,0,0,0,0,0,0,0,0,0,0,0,0,0,0,0,0,0,0,0,0,0,0,0,0,0,0,0,0,0,0,0,0,0,0,0,0}},
{10,0,1,0,{10,0,0,0},{0,0,0,0},{26,0,0,0},{0,9,18,1,10,19,2,11,20,3,12,21,4,13,22,5,14,23,6,15,24,7,16,25,8,17,0,0,0,0,0,0,0,0,0,0,0,0,0,0,0,0,0,0,0,0,0,0,0,0,0,0,0,0,0,0,0,0,0,0,0,0,0,0}},
{11,0,1,0,{11,0,0,0},{0,0,0,0},{26,0,0,0},{0,9,18,1,10,19,2,11,20,3,12,21,4,13,22,5,14,23,6,15,24,7,16,25,8,17,0,0,0,0,0,0,0,0,0,0,0,0,0,0,0,0,0,0,0,0,0,0,0,0,0,0,0,0,0,0,0,0,0,0,0,0,0,0}},
{8,1,1,0,{8,0,0,0},{0,0,0,0},{26,0,0,0},{27,36,45,28,37,46,29,38,47,30,39,48,31,40,49,32,41,50,33,42,51,34,43,26,35,44,0,0,0,0,0,0,0,0,0,0,0,0,0,0,0,0,0,0,0,0,0,0,0,0,0,0,0,0,0,0,0,0,0,0,0,0,0,0}},
{9,1,1,0,{9,0,0,0},{0,0,0,0},{26,0,0,0},{27,36,45,28,37,46,29,38,47,30,39,48,31,40,49,32,41,50,33,42,51,34,43,26,35,44,0,0,0,0,0,0,0,0,0,0,0,0,0,0,0,0,0,0,0,0,0,0,0,0,0,0,0,0,0,0,0,0,0,0,0,0,0,0}},
{10,1,1,0,{10,0,0,0},{0,0,0,0},{26,0,0,0},{27,36,45,28,37,46,29,38,47,30,39,48,31,40,49,32,41,50,33,42,51,34,43,26,35,44,0,0,0,0,0,0,0,0,0,0,0,0,0,0,0,0,0,0,0,0,0,0,0,0,0,0,0,0,0,0,0,0,0,0,0,0,0,0}},
{11,1,1,0,{11,0,0,0},{0,0,0,0},{26,0,0,0},{27,36,45,28,37,46,29,38,47,30,39,48,31,40,49,32,41,50,33,42,51,34,43,26,35,44,0,0,0,0,0,0,0,0,0,0,0,0,0,0,0,0,0,0,0,0,0,0,0,0,0,0,0,0,0,0,0,0,0,0,0,0,0,0}},
{8,2,2,0,{8,8,0,0},{0,1,0,0},{20,3,0,0},{54,63,55,64,56,65,57,66,58,67,59,68,60,69,52,61,70,53,62,71,2,3,4,0,0,0,0,0,0,0,0,0,0,0,0,0,0,0,0,0,0,0,0,0,0,0,0,0,0,0,0,0,0,0,0,0,0,0,0,0,0,0,0,0}},
{9,2,2,0,{9,9,0,0},{0,1,0,0},{20,3,0,0},{54,63,55,64,56,65,57,66,58,67,59,68,60,69,52,61,70,53,62,71,2,3,4,0,0,0,0,0,0,0,0,0,0,0,0,0,0,0,0,0,0,0,0,0,0,0,0,0,0,0,0,0,0,0,0,0,0,0,0,0,0,0,0,0}},
{10,2,2,0,{10,10,0,0},{0,1,0,0},{20,3,0,0},{54,63,55,64,56,65,57,66,58,67,59,68,60,69,52,61,70,53,62,71,2,3,4,0,0,0,0,0,0,0,0,0,0,0,0,0,0,0,0,0,0,0,0,0,0,0,0,0,0,0,0,0,0,0,0,0,0,0,0,0,0,0,0,0}},
{11,2,2,0,{11,11,0,0},{0,1,0,0},{20,3,0,0},{54,63,55,64,56,65,57,66,58,67,59,68,60,69,52,61,70,53,62,71,2,3,4,0,0,0,0,0,0,0,0,0,0,0,0,0,0,0,0,0,0,0,0,0,0,0,0,0,0,0,0,0,0,0,0,0,0,0,0,0,0,0,0,0}},
{8,3,1,0,{8,0,0,0},{1,0,0,0},{26,0,0,0},{11,20,29,38,12,21,30,13,22,31,5,14,23,32,6,15,24,33,7,16,25,34,8,17,26,35,0,0,0,0,0,0,0,0,0,0,0,0,0,0,0,0,0,0,0,0,0,0,0,0,0,0,0,0,0,0,0,0,0,0,0,0,0,0}},
{9,3,1,0,{9,0,0,0},{1,0,0,0},{26,0,0,0},{11,20,29,38,12,21,30,13,22,31,5,14,23,32,6,15,24,33,7,16,25,34,8,17,26,35,0,0,0,0,0,0,0,0,0,0,0,0,0,0,0,0,0,0,0,0,0,0,0,0,0,0,0,0,0,0,0,0,0,0,0,0,0,0}},
{10,3,1,0,{10,0,0,0},{1,0,0,0},{26,0,0,0},{11,20,29,38,12,21,30,13,22,31,5,14,23,32,6,15,24,33,7,16,25,34,8,17,26,35,0,0,0,0,0,0,0,0,0,0,0,0,0,0,0,0,0,0,0,0,0,0,0,0,0,0,0,0,0,0,0,0,0,0,0,0,0,0}},
{11,3,1,0,{11,0,0,0},{1,0,0,0},{26,0,0,0},{11,20,29,38,12,21,30,13,22,31,5,14,23,32,6,15,24,33,7,16,25,34,8,17,26,35,0,0,0,0,0,0,0,0,0,0,0,0,0,0,0,0,0,0,0,0,0,0,0,0,0,0,0,0,0,0,0,0,0,0,0,0,0,0}},
{8,4,1,0,{8,0,0,0},{1,0,0,0},{26,0,0,0},{55,64,47,56,65,39,48,57,66,40,49,58,67,41,50,59,68,42,51,60,43,52,61,44,53,62,0,0,0,0,0,0,0,0,0,0,0,0,0,0,0,0,0,0,0,0,0,0,0,0,0,0,0,0,0,0,0,0,0,0,0,0,0,0}},
{9,4,1,0,{9,0,0,0},{1,0,0,0},{26,0,0,0},{55,64,47,56,65,39,48,57,66,40,49,58,67,41,50,59,68,42,51,60,43,52,61,44,53,62,0,0,0,0,0,0,0,0,0,0,0,0,0,0,0,0,0,0,0,0,0,0,0,0,0,0,0,0,0,0,0,0,0,0,0,0,0,0}},
{10,4,1,0,{10,0,0,0},{1,0,0,0},{26,0,0,0},{55,64,47,56,65,39,48,57,66,40,49,58,67,41,50,59,68,42,51,60,43,52,61,44,53,62,0,0,0,0,0,0,0,0,0,0,0,0,0,0,0,0,0,0,0,0,0,0,0,0,0,0,0,0,0,0,0,0,0,0,0,0,0,0}},
{11,4,1,0,{11,0,0,0},{1,0,0,0},{26,0,0,0},{55,64,47,56,65,39,48,57,66,40,49,58,67,41,50,59,68,42,51,60,43,52,61,44,53,62,0,0,0,0,0,0,0,0,0,0,0,0,0,0,0,0,0,0,0,0,0,0,0,0,0,0,0,0,0,0,0,0,0,0,0,0,0,0}},
{8,5,2,0,{8,8,0,0},{2,1,0,0},{20,3,0,0},{0,9,18,1,10,19,2,11,3,12,4,13,5,14,6,15,7,16,8,17,69,70,71,0,0,0,0,0,0,0,0,0,0,0,0,0,0,0,0,0,0,0,0,0,0,0,0,0,0,0,0,0,0,0,0,0,0,0,0,0,0,0,0,0}},
{9,5,2,0,{9,9,0,0},{2,1,0,0},{20,3,0,0},{0,9,18,1,10,19,2,11,3,12,4,13,5,14,6,15,7,16,8,17,69,70,71,0,0,0,0,0,0,0,0,0,0,0,0,0,0,0,0,0,0,0,0,0,0,0,0,0,0,0,0,0,0,0,0,0,0,0,0,0,0,0,0,0}},
{10,5,2,0,{10,10,0,0},{2,1,0,0},{20,3,0,0},{0,9,18,1,10,19,2,11,3,12,4,13,5,14,6,15,7,16,8,17,69,70,71,0,0,0,0,0,0,0,0,0,0,0,0,0,0,0,0,0,0,0,0,0,0,0,0,0,0,0,0,0,0,0,0,0,0,0,0,0,0,0,0,0}},
{11,5,2,0,{11,11,0,0},{2,1,0,0},{20,3,0,0},{0,9,18,1,10,19,2,11,3,12,4,13,5,14,6,15,7,16,8,17,69,70,71,0,0,0,0,0,0,0,0,0,0,0,0,0,0,0,0,0,0,0,0,0,0,0,0,0,0,0,0,0,0,0,0,0,0,0,0,0,0,0,0,0}},
{8,6,1,0,{8,0,0,0},{2,0,0,0},{26,0,0,0},{27,36,45,28,37,20,29,38,21,30,39,22,31,40,23,32,41,24,33,42,25,34,43,26,35,44,0,0,0,0,0,0,0,0,0,0,0,0,0,0,0,0,0,0,0,0,0,0,0,0,0,0,0,0,0,0,0,0,0,0,0,0,0,0}},
{9,6,1,0,{9,0,0,0},{2,0,0,0},{26,0,0,0},{27,36,45,28,37,20,29,38,21,30,39,22,31,40,23,32,41,24,33,42,25,34,43,26,35,44,0,0,0,0,0,0,0,0,0,0,0,0,0,0,0,0,0,0,0,0,0,0,0,0,0,0,0,0,0,0,0,0,0,0,0,0,0,0}},
{10,6,1,0,{10,0,0,0},{2,0,0,0},{26,0,0,0},{27,36,45,28,37,20,29,38,21,30,39,22,31,40,23,32,41,24,33,42,25,34,43,26,35,44,0,0,0,0,0,0,0,0,0,0,0,0,0,0,0,0,0,0,0,0,0,0,0,0,0,0,0,0,0,0,0,0,0,0,0,0,0,0}},
{11,6,1,0,{11,0,0,0},{2,0,0,0},{26,0,0,0},{27,36,45,28,37,20,29,38,21,30,39,22,31,40,23,32,41,24,33,42,25,34,43,26,35,44,0,0,0,0,0,0,0,0,0,0,0,0,0,0,0,0,0,0,0,0,0,0,0,0,0,0,0,0,0,0,0,0,0,0,0,0,0,0}},
{8,7,1,0,{8,0,0,0},{2,0,0,0},{26,0,0,0},{54,63,46,55,64,47,56,65,48,57,66,49,58,67,50,59,68,51,60,69,52,61,70,53,62,71,0,0,0,0,0,0,0,0,0,0,0,0,0,0,0,0,0,0,0,0,0,0,0,0,0,0,0,0,0,0,0,0,0,0,0,0,0,0}},
{9,7,1,0,{9,0,0,0},{2,0,0,0},{26,0,0,0},{54,63,46,55,64,47,56,65,48,57,66,49,58,67,50,59,68,51,60,69,52,61,70,53,62,71,0,0,0,0,0,0,0,0,0,0,0,0,0,0,0,0,0,0,0,0,0,0,0,0,0,0,0,0,0,0,0,0,0,0,0,0,0,0}},
{10,7,1,0,{10,0,0,0},{2,0,0,0},{26,0,0,0},{54,63,46,55,64,47,56,65,48,57,66,49,58,67,50,59,68,51,60,69,52,61,70,53,62,71,0,0,0,0,0,0,0,0,0,0,0,0,0,0,0,0,0,0,0,0,0,0,0,0,0,0,0,0,0,0,0,0,0,0,0,0,0,0}},
{11,7,1,0,{11,0,0,0},{2,0,0,0},{26,0,0,0},{54,63,46,55,64,47,56,65,48,57,66,49,58,67,50,59,68,51,60,69,52,61,70,53,62,71,0,0,0,0,0,0,0,0,0,0,0,0,0,0,0,0,0,0,0,0,0,0,0,0,0,0,0,0,0,0,0,0,0,0,0,0,0,0}},
{12,0,1,0,{12,0,0,0},{0,0,0,0},{26,0,0,0},{0,9,18,1,10,19,2,11,20,3,12,21,4,13,22,5,14,23,6,15,24,7,16,25,8,17,0,0,0,0,0,0,0,0,0,0,0,0,0,0,0,0,0,0,0,0,0,0,0,0,0,0,0,0,0,0,0,0,0,0,0,0,0,0}},
{13,0,1,0,{13,0,0,0},{0,0,0,0},{26,0,0,0},{0,9,18,1,10,19,2,11,20,3,12,21,4,13,22,5,14,23,6,15,24,7,16,25,8,17,0,0,0,0,0,0,0,0,0,0,0,0,0,0,0,0,0,0,0,0,0,0,0,0,0,0,0,0,0,0,0,0,0,0,0,0,0,0}},
{14,0,1,0,{14,0,0,0},{0,0,0,0},{26,0,0,0},{0,9,18,1,10,19,2,11,20,3,12,21,4,13,22,5,14,23,6,15,24,7,16,25,8,17,0,0,0,0,0,0,0,0,0,0,0,0,0,0,0,0,0,0,0,0,0,0,0,0,0,0,0,0,0,0,0,0,0,0,0,0,0,0}},
{15,0,1,0,{15,0,0,0},{0,0,0,0},{26,0,0,0},{0,9,18,1,10,19,2,11,20,3,12,21,4,13,22,5,14,23,6,15,24,7,16,25,8,17,0,0,0,0,0,0,0,0,0,0,0,0,0,0,0,0,0,0,0,0,0,0,0,0,0,0,0,0,0,0,0,0,0,0,0,0,0,0}},
{12,1,1,0,{12,0,0,0},{0,0,0,0},{26,0,0,0},{27,36,45,28,37,46,29,38,47,30,39,48,31,40,49,32,41,50,33,42,51,34,43,26,35,44,0,0,0,0,0,0,0,0,0,0,0,0,0,0,0,0,0,0,0,0,0,0,0,0,0,0,0,0,0,0,0,0,0,0,0,0,0,0}},
{13,1,1,0,{13,0,0,0},{0,0,0,0},{26,0,0,0},{27,36,45,28,37,46,29,38,47,30,39,48,31,40,49,32,41,50,33,42,51,34,43,26,35,44,0,0,0,0,0,0,0,0,0,0,0,0,0,0,0,0,0,0,0,0,0,0,0,0,0,0,0,0,0,0,0,0,0,0,0,0,0,0}},
{14,1,1,0,{14,0,0,0},{0,0,0,0},{26,0,0,0},{27,36,45,28,37,46,29,38,47,30,39,48,31,40,49,32,41,50,33,42,51,34,43,26,35,44,0,0,0,0,0,0,0,0,0,0,0,0,0,0,0,0,0,0,0,0,0,0,0,0,0,0,0,0,0,0,0,0,0,0,0,0,0,0}},
{15,1,1,0,{15,0,0,0},{0,0,0,0},{26,0,0,0},{27,36,45,28,37,46,29,38,47,30,39,48,31,40,49,32,41,50,33,42,51,34,43,26,35,44,0,0,0,0,0,0,0,0,0,0,0,0,0,0,0,0,0,0,0,0,0,0,0,0,0,0,0,0,0,0,0,0,0,0,0,0,0,0}},
{12,2,2,0,{12,12,0,0},{0,1,0,0},{20,3,0,0},{54,63,55,64,56,65,57,66,58,67,59,68,60,69,52,61,70,53,62,71,2,3,4,0,0,0,0,0,0,0,0,0,0,0,0,0,0,0,0,0,0,0,0,0,0,0,0,0,0,0,0,0,0,0,0,0,0,0,0,0,0,0,0,0}},
{13,2,2,0,{13,13,0,0},{0,1,0,0},{20,3,0,0},{54,63,55,64,56,65,57,66,58,67,59,68,60,69,52,61,70,53,62,71,2,3,4,0,0,0,0,0,0,0,0,0,0,0,0,0,0,0,0,0,0,0,0,0,0,0,0,0,0,0,0,0,0,0,0,0,0,0,0,0,0,0,0,0}},
{14,2,2,0,{14,14,0,0},{0,1,0,0},{20,3,0,0},{54,63,55,64,56,65,57,66,58,67,59,68,60,69,52,61,70,53,62,71,2,3,4,0,0,0,0,0,0,0,0,0,0,0,0,0,0,0,0,0,0,0,0,0,0,0,0,0,0,0,0,0,0,0,0,0,0,0,0,0,0,0,0,0}},
{15,2,2,0,{15,15,0,0},{0,1,0,0},{20,3,0,0},{54,63,55,64,56,65,57,66,58,67,59,68,60,69,52,61,70,53,62,71,2,3,4,0,0,0,0,0,0,0,0,0,0,0,0,0,0,0,0,0,0,0,0,0,0,0,0,0,0,0,0,0,0,0,0,0,0,0,0,0,0,0,0,0}},
{12,3,1,0,{12,0,0,0},{1,0,0,0},{26,0,0,0},{11,20,29,38,12,21,30,13,22,31,5,14,23,32,6,15,24,33,7,16,25,34,8,17,26,35,0,0,0,0,0,0,0,0,0,0,0,0,0,0,0,0,0,0,0,0,0,0,0,0,0,0,0,0,0,0,0,0,0,0,0,0,0,0}},
{13,3,1,0,{13,0,0,0},{1,0,0,0},{26,0,0,0},{11,20,29,38,12,21,30,13,22,31,5,14,23,32,6,15,24,33,7,16,25,34,8,17,26,35,0,0,0,0,0,0,0,0,0,0,0,0,0,0,0,0,0,0,0,0,0,0,0,0,0,0,0,0,0,0,0,0,0,0,0,0,0,0}},
{14,3,1,0,{14,0,0,0},{1,0,0,0},{26,0,0,0},{11,20,29,38,12,21,30,13,22,31,5,14,23,32,6,15,24,33,7,16,25,34,8,17,26,35,0,0,0,0,0,0,0,0,0,0,0,0,0,0,0,0,0,0,0,0,0,0,0,0,0,0,0,0,0,0,0,0,0,0,0,0,0,0}},
{15,3,1,0,{15,0,0,0},{1,0,0,0},{26,0,0,0},{11,20,29,38,12,21,30,13,22,31,5,14,23,32,6,15,24,33,7,16,25,34,8,17,26,35,0,0,0,0,0,0,0,0,0,0,0,0,0,0,0,0,0,0,0,0,0,0,0,0,0,0,0,0,0,0,0,0,0,0,0,0,0,0}},
{12,4,1,0,{12,0,0,0},{1,0,0,0},{26,0,0,0},{55,64,47,56,65,39,48,57,66,40,49,58,67,41,50,59,68,42,51,60,43,52,61,44,53,62,0,0,0,0,0,0,0,0,0,0,0,0,0,0,0,0,0,0,0,0,0,0,0,0,0,0,0,0,0,0,0,0,0,0,0,0,0,0}},
{13,4,1,0,{13,0,0,0},{1,0,0,0},{26,0,0,0},{55,64,47,56,65,39,48,57,66,40,49,58,67,41,50,59,68,42,51,60,43,52,61,44,53,62,0,0,0,0,0,0,0,0,0,0,0,0,0,0,0,0,0,0,0,0,0,0,0,0,0,0,0,0,0,0,0,0,0,0,0,0,0,0}},
{14,4,1,0,{14,0,0,0},{1,0,0,0},{26,0,0,0},{55,64,47,56,65,39,48,57,66,40,49,58,67,41,50,59,68,42,51,60,43,52,61,44,53,62,0,0,0,0,0,0,0,0,0,0,0,0,0,0,0,0,0,0,0,0,0,0,0,0,0,0,0,0,0,0,0,0,0,0,0,0,0,0}},
{15,4,1,0,{15,0,0,0},{1,0,0,0},{26,0,0,0},{55,64,47,56,65,39,48,57,66,40,49,58,67,41,50,59,68,42,51,60,43,52,61,44,53,62,0,0,0,0,0,0,0,0,0,0,0,0,0,0,0,0,0,0,0,0,0,0,0,0,0,0,0,0,0,0,0,0,0,0,0,0,0,0}},
{12,5,2,0,{12,12,0,0},{2,1,0,0},{20,3,0,0},{0,9,18,1,10,19,2,11,3,12,4,13,5,14,6,15,7,16,8,17,69,70,71,0,0,0,0,0,0,0,0,0,0,0,0,0,0,0,0,0,0,0,0,0,0,0,0,0,0,0,0,0,0,0,0,0,0,0,0,0,0,0,0,0}},
{13,5,2,0,{13,13,0,0},{2,1,0,0},{20,3,0,0},{0,9,18,1,10,19,2,11,3,12,4,13,5,14,6,15,7,16,8,17,69,70,71,0,0,0,0,0,0,0,0,0,0,0,0,0,0,0,0,0,0,0,0,0,0,0,0,0,0,0,0,0,0,0,0,0,0,0,0,0,0,0,0,0}},
{14,5,2,0,{14,14,0,0},{2,1,0,0},{20,3,0,0},{0,9,18,1,10,19,2,11,3,12,4,13,5,14,6,15,7,16,8,17,69,70,71,0,0,0,0,0,0,0,0,0,0,0,0,0,0,0,0,0,0,0,0,0,0,0,0,0,0,0,0,0,0,0,0,0,0,0,0,0,0,0,0,0}},
{15,5,2,0,{15,15,0,0},{2,1,0,0},{20,3,0,0},{0,9,18,1,10,19,2,11,3,12,4,13,5,14,6,15,7,16,8,17,69,70,71,0,0,0,0,0,0,0,0,0,0,0,0,0,0,0,0,0,0,0,0,0,0,0,0,0,0,0,0,0,0,0,0,0,0,0,0,0,0,0,0,0}},
{12,6,1,0,{12,0,0,0},{2,0,0,0},{26,0,0,0},{27,36,45,28,37,20,29,38,21,30,39,22,31,40,23,32,41,24,33,42,25,34,43,26,35,44,0,0,0,0,0,0,0,0,0,0,0,0,0,0,0,0,0,0,0,0,0,0,0,0,0,0,0,0,0,0,0,0,0,0,0,0,0,0}},
{13,6,1,0,{13,0,0,0},{2,0,0,0},{26,0,0,0},{27,36,45,28,37,20,29,38,21,30,39,22,31,40,23,32,41,24,33,42,25,34,43,26,35,44,0,0,0,0,0,0,0,0,0,0,0,0,0,0,0,0,0,0,0,0,0,0,0,0,0,0,0,0,0,0,0,0,0,0,0,0,0,0}},
{14,6,1,0,{14,0,0,0},{2,0,0,0},{26,0,0,0},{27,36,45,28,37,20,29,38,21,30,39,22,31,40,23,32,41,24,33,42,25,34,43,26,35,44,0,0,0,0,0,0,0,0,0,0,0,0,0,0,0,0,0,0,0,0,0,0,0,0,0,0,0,0,0,0,0,0,0,0,0,0,0,0}},
{15,6,1,0,{15,0,0,0},{2,0,0,0},{26,0,0,0},{27,36,45,28,37,20,29,38,21,30,39,22,31,40,23,32,41,24,33,42,25,34,43,26,35,44,0,0,0,0,0,0,0,0,0,0,0,0,0,0,0,0,0,0,0,0,0,0,0,0,0,0,0,0,0,0,0,0,0,0,0,0,0,0}},
{12,7,1,0,{12,0,0,0},{2,0,0,0},{26,0,0,0},{54,63,46,55,64,47,56,65,48,57,66,49,58,67,50,59,68,51,60,69,52,61,70,53,62,71,0,0,0,0,0,0,0,0,0,0,0,0,0,0,0,0,0,0,0,0,0,0,0,0,0,0,0,0,0,0,0,0,0,0,0,0,0,0}},
{13,7,1,0,{13,0,0,0},{2,0,0,0},{26,0,0,0},{54,63,46,55,64,47,56,65,48,57,66,49,58,67,50,59,68,51,60,69,52,61,70,53,62,71,0,0,0,0,0,0,0,0,0,0,0,0,0,0,0,0,0,0,0,0,0,0,0,0,0,0,0,0,0,0,0,0,0,0,0,0,0,0}},
{14,7,1,0,{14,0,0,0},{2,0,0,0},{26,0,0,0},{54,63,46,55,64,47,56,65,48,57,66,49,58,67,50,59,68,51,60,69,52,61,70,53,62,71,0,0,0,0,0,0,0,0,0,0,0,0,0,0,0,0,0,0,0,0,0,0,0,0,0,0,0,0,0,0,0,0,0,0,0,0,0,0}},
{15,7,1,0,{15,0,0,0},{2,0,0,0},{26,0,0,0},{54,63,46,55,64,47,56,65,48,57,66,49,58,67,50,59,68,51,60,69,52,61,70,53,62,71,0,0,0,0,0,0,0,0,0,0,0,0,0,0,0,0,0,0,0,0,0,0,0,0,0,0,0,0,0,0,0,0,0,0,0,0,0,0}},
{255,255,4,0,{8,9,10,11},{1,1,1,1},{14,14,14,14},{0,9,18,27,36,45,54,63,1,10,19,28,37,46,0,9,18,27,36,45,54,63,1,10,19,28,37,46,0,9,18,27,36,45,54,63,1,10,19,28,37,46,0,9,18,27,36,45,54,63,1,10,19,28,37,46,0,0,0,0,0,0,0,0}},
{255,255,4,0,{12,13,14,15},{1,1,1,1},{14,14,14,14},{0,9,18,27,36,45,54,63,1,10,19,28,37,46,0,9,18,27,36,45,54,63,1,10,19,28,37,46,0,9,18,27,36,45,54,63,1,10,19,28,37,46,0,9,18,27,36,45,54,63,1,10,19,28,37,46,0,0,0,0,0,0,0,0}}
};

__device__ __align__(1024) uint8_t g_h[(size_t)S_ * F_ * 2];
__device__ unsigned long long g_count;
__device__ unsigned g_hflag[16 * 8 * 32];
#define TS(arr, idx)

__device__ __forceinline__ uint32_t smem_u32(const void* p) { return (uint32_t)__cvta_generic_to_shared(p); }
__device__ __forceinline__ void mbar_init(uint32_t bar, uint32_t count) { asm volatile("mbarrier.init.shared::cta.b64 [%0], %1;" :: "r"(bar), "r"(count)); }
__device__ __forceinline__ void mbar_expect_tx(uint32_t bar, uint32_t bytes) { asm volatile("mbarrier.arrive.expect_tx.shared::cta.b64 _, [%0], %1;" :: "r"(bar), "r"(bytes) : "memory"); }
__device__ __forceinline__ void mbar_arrive(uint32_t bar) { asm volatile("mbarrier.arrive.shared::cta.b64 _, [%0];" :: "r"(bar) : "memory"); }
__device__ __forceinline__ bool mbar_try_wait(uint32_t bar, uint32_t parity) {
  uint32_t ok;
  asm volatile("{\n.reg .pred p;\nmbarrier.try_wait.parity.shared::cta.b64 p, [%1], %2;\nselp.u32 %0, 1, 0, p;\n}" : "=r"(ok) : "r"(bar), "r"(parity) : "memory");
  return ok;
}
__device__ __forceinline__ bool mbar_test_wait(uint32_t bar, uint32_t parity) {
  uint32_t ok;
  asm volatile("{\n.reg .pred p;\nmbarrier.test_wait.parity.shared::cta.b64 p, [%1], %2;\nselp.u32 %0, 1, 0, p;\n}" : "=r"(ok) : "r"(bar), "r"(parity) : "memory");
  return ok;
}
__device__ __forceinline__ void mbar_wait(uint32_t bar, uint32_t parity) {
  if (mbar_try_wait(bar, parity)) return;
  #pragma unroll 1
  for (uint32_t i = 0; i < (1u << 24); i++) { if (mbar_try_wait(bar, parity)) return; }
  __trap();
}
__device__ __forceinline__ void tma_load_2d(uint32_t dst, const CUtensorMap* tm, int c0, int c1, uint32_t bar) {
  asm volatile("cp.async.bulk.tensor.2d.shared::cluster.global.mbarrier::complete_tx::bytes [%0], [%1, {%3, %4}], [%2];"
    :: "r"(dst), "l"((uint64_t)tm), "r"(bar), "r"(c0), "r"(c1) : "memory");
}
__device__ __forceinline__ void tma_load_5d(uint32_t dst, const CUtensorMap* tm, int c3, int c4, uint32_t bar) {
  asm volatile("cp.async.bulk.tensor.5d.shared::cluster.global.mbarrier::complete_tx::bytes [%0], [%1, {%5, %5, %5, %3, %4}], [%2];"
    :: "r"(dst), "l"((uint64_t)tm), "r"(bar), "r"(c3), "r"(c4), "r"(0) : "memory");
}
__device__ __forceinline__ void prefetch_tmap(const CUtensorMap* tm) { asm volatile("prefetch.tensormap [%0];" :: "l"((uint64_t)tm) : "memory"); }
__device__ __forceinline__ void bulk_load(uint32_t dst, const void* src, uint32_t bytes, uint32_t bar) {
  asm volatile("cp.async.bulk.shared::cluster.global.mbarrier::complete_tx::bytes [%0], [%1], %2, [%3];"
    :: "r"(dst), "l"((uint64_t)src), "r"(bytes), "r"(bar) : "memory");
}
__device__ __forceinline__ void wgmma_fence() { asm volatile("wgmma.fence.sync.aligned;" ::: "memory"); }
__device__ __forceinline__ void wgmma_commit() { asm volatile("wgmma.commit_group.sync.aligned;" ::: "memory"); }
template<int N> __device__ __forceinline__ void wgmma_wait() { asm volatile("wgmma.wait_group.sync.aligned %0;" :: "n"(N) : "memory"); }
template<int R> __device__ __forceinline__ void reg_alloc() { asm volatile("setmaxnreg.inc.sync.aligned.u32 %0;" :: "n"(R)); }
template<int R> __device__ __forceinline__ void reg_dealloc() { asm volatile("setmaxnreg.dec.sync.aligned.u32 %0;" :: "n"(R)); }
__device__ __forceinline__ uint32_t desc_lo(uint32_t addr, uint32_t lbo_bytes) { return ((addr & 0x3FFFF) >> 4) | ((lbo_bytes >> 4) << 16); }
constexpr uint32_t desc_hi(uint32_t sbo_bytes, uint32_t swz) { return (sbo_bytes >> 4) | (swz << 30); }
constexpr uint32_t HI_SW128 = desc_hi(1024, 1), HI_NOSW = desc_hi(128, 0);
__device__ __forceinline__ unsigned ld_acquire(const unsigned* p) { unsigned v; asm volatile("ld.acquire.gpu.global.u32 %0, [%1];" : "=r"(v) : "l"(p) : "memory"); return v; }
__device__ __forceinline__ void st_release(unsigned* p, unsigned v) { asm volatile("st.release.gpu.global.u32 [%0], %1;" :: "l"(p), "r"(v) : "memory"); }
__device__ __forceinline__ void fence_proxy_async_global() { asm volatile("fence.proxy.async.global;" ::: "memory"); }
__device__ __forceinline__ uint32_t lds_acquire(uint32_t a) { uint32_t v; asm volatile("ld.acquire.cta.shared.u32 %0, [%1];" : "=r"(v) : "r"(a) : "memory"); return v; }
__device__ __forceinline__ void sts_release(uint32_t a, uint32_t v) { asm volatile("st.release.cta.shared.u32 [%0], %1;" :: "r"(a), "r"(v) : "memory"); }
__device__ __forceinline__ uint32_t lds_u8(uint32_t a) { uint32_t v; asm volatile("ld.shared.u8 %0, [%1];" : "=r"(v) : "r"(a)); return v; }
__device__ __forceinline__ uint32_t cvt_bf16x2(float lo, float hi) { uint32_t r; asm("cvt.rn.bf16x2.f32 %0, %1, %2;" : "=r"(r) : "f"(hi), "f"(lo)); return r; }
__device__ __forceinline__ uint32_t cvt_relu_bf16x2(float lo, float hi) { uint32_t r; asm("cvt.rn.relu.bf16x2.f32 %0, %1, %2;" : "=r"(r) : "f"(hi), "f"(lo)); return r; }
__device__ __forceinline__ uint32_t mul_bf16x2(uint32_t a, uint32_t b) { uint32_t r; asm("mul.rn.bf16x2 %0, %1, %2;" : "=r"(r) : "r"(a), "r"(b)); return r; }

template<uint32_t HA, uint32_t HB, int TA, int TB> __device__ __forceinline__ void wgmma2_n128(float (&d)[64], uint32_t loA, uint32_t loB, int scaleD) {
  asm volatile("{\n.reg .pred p;\n.reg .b64 da, db;\n"
  "mov.b64 da, {%64, %69};\nmov.b64 db, {%65, %70};\n"
  "setp.ne.b32 p, %66, 0;\n"
  "wgmma.mma_async.sync.aligned.m64n128k16.f32.bf16.bf16 "
  "{%0, %1, %2, %3, %4, %5, %6, %7, %8, %9, %10, %11, %12, %13, %14, %15, %16, %17, %18, %19, %20, %21, %22, %23, %24, %25, %26, %27, %28, %29, %30, %31, %32, %33, %34, %35, %36, %37, %38, %39, %40, %41, %42, %43, %44, %45, %46, %47, %48, %49, %50, %51, %52, %53, %54, %55, %56, %57, %58, %59, %60, %61, %62, %63}, "
  "da, db, p, 1, 1, %67, %68;\n}\n"
  : "+f"(d[0]), "+f"(d[1]), "+f"(d[2]), "+f"(d[3]), "+f"(d[4]), "+f"(d[5]), "+f"(d[6]), "+f"(d[7]), "+f"(d[8]), "+f"(d[9]), "+f"(d[10]), "+f"(d[11]), "+f"(d[12]), "+f"(d[13]), "+f"(d[14]), "+f"(d[15]), "+f"(d[16]), "+f"(d[17]), "+f"(d[18]), "+f"(d[19]), "+f"(d[20]), "+f"(d[21]), "+f"(d[22]), "+f"(d[23]), "+f"(d[24]), "+f"(d[25]), "+f"(d[26]), "+f"(d[27]), "+f"(d[28]), "+f"(d[29]), "+f"(d[30]), "+f"(d[31]), "+f"(d[32]), "+f"(d[33]), "+f"(d[34]), "+f"(d[35]), "+f"(d[36]), "+f"(d[37]), "+f"(d[38]), "+f"(d[39]), "+f"(d[40]), "+f"(d[41]), "+f"(d[42]), "+f"(d[43]), "+f"(d[44]), "+f"(d[45]), "+f"(d[46]), "+f"(d[47]), "+f"(d[48]), "+f"(d[49]), "+f"(d[50]), "+f"(d[51]), "+f"(d[52]), "+f"(d[53]), "+f"(d[54]), "+f"(d[55]), "+f"(d[56]), "+f"(d[57]), "+f"(d[58]), "+f"(d[59]), "+f"(d[60]), "+f"(d[61]), "+f"(d[62]), "+f"(d[63])
  : "r"(loA), "r"(loB), "r"(scaleD), "n"(TA), "n"(TB), "n"(HA), "n"(HB));
}
template<uint32_t HA, uint32_t HB, int TA, int TB> __device__ __forceinline__ void wgmma2_n192(float (&d)[96], uint32_t loA, uint32_t loB, int scaleD) {
  asm volatile("{\n.reg .pred p;\n.reg .b64 da, db;\n"
  "mov.b64 da, {%96, %101};\nmov.b64 db, {%97, %102};\n"
  "setp.ne.b32 p, %98, 0;\n"
  "wgmma.mma_async.sync.aligned.m64n192k16.f32.bf16.bf16 "
  "{%0, %1, %2, %3, %4, %5, %6, %7, %8, %9, %10, %11, %12, %13, %14, %15, %16, %17, %18, %19, %20, %21, %22, %23, %24, %25, %26, %27, %28, %29, %30, %31, %32, %33, %34, %35, %36, %37, %38, %39, %40, %41, %42, %43, %44, %45, %46, %47, %48, %49, %50, %51, %52, %53, %54, %55, %56, %57, %58, %59, %60, %61, %62, %63, %64, %65, %66, %67, %68, %69, %70, %71, %72, %73, %74, %75, %76, %77, %78, %79, %80, %81, %82, %83, %84, %85, %86, %87, %88, %89, %90, %91, %92, %93, %94, %95}, "
  "da, db, p, 1, 1, %99, %100;\n}\n"
  : "+f"(d[0]), "+f"(d[1]), "+f"(d[2]), "+f"(d[3]), "+f"(d[4]), "+f"(d[5]), "+f"(d[6]), "+f"(d[7]), "+f"(d[8]), "+f"(d[9]), "+f"(d[10]), "+f"(d[11]), "+f"(d[12]), "+f"(d[13]), "+f"(d[14]), "+f"(d[15]), "+f"(d[16]), "+f"(d[17]), "+f"(d[18]), "+f"(d[19]), "+f"(d[20]), "+f"(d[21]), "+f"(d[22]), "+f"(d[23]), "+f"(d[24]), "+f"(d[25]), "+f"(d[26]), "+f"(d[27]), "+f"(d[28]), "+f"(d[29]), "+f"(d[30]), "+f"(d[31]), "+f"(d[32]), "+f"(d[33]), "+f"(d[34]), "+f"(d[35]), "+f"(d[36]), "+f"(d[37]), "+f"(d[38]), "+f"(d[39]), "+f"(d[40]), "+f"(d[41]), "+f"(d[42]), "+f"(d[43]), "+f"(d[44]), "+f"(d[45]), "+f"(d[46]), "+f"(d[47]), "+f"(d[48]), "+f"(d[49]), "+f"(d[50]), "+f"(d[51]), "+f"(d[52]), "+f"(d[53]), "+f"(d[54]), "+f"(d[55]), "+f"(d[56]), "+f"(d[57]), "+f"(d[58]), "+f"(d[59]), "+f"(d[60]), "+f"(d[61]), "+f"(d[62]), "+f"(d[63]), "+f"(d[64]), "+f"(d[65]), "+f"(d[66]), "+f"(d[67]), "+f"(d[68]), "+f"(d[69]), "+f"(d[70]), "+f"(d[71]), "+f"(d[72]), "+f"(d[73]), "+f"(d[74]), "+f"(d[75]), "+f"(d[76]), "+f"(d[77]), "+f"(d[78]), "+f"(d[79]), "+f"(d[80]), "+f"(d[81]), "+f"(d[82]), "+f"(d[83]), "+f"(d[84]), "+f"(d[85]), "+f"(d[86]), "+f"(d[87]), "+f"(d[88]), "+f"(d[89]), "+f"(d[90]), "+f"(d[91]), "+f"(d[92]), "+f"(d[93]), "+f"(d[94]), "+f"(d[95])
  : "r"(loA), "r"(loB), "r"(scaleD), "n"(TA), "n"(TB), "n"(HA), "n"(HB));
}

constexpr uint32_t B_WFULL = 0, B_WEMPTY = 64, B_XFULL = 128, B_P2FULL = 256, B_P2EMPTY = 320, B_HDONE = 384  , B_ZDONE = 464, B_TABLE = 472,
                   B_EPOCH = 480, B_READY = 512  , B_SCHED = 640  ;

template<int H, int R>
__device__ __forceinline__ void h_quarter(const float (&acc)[64], uint8_t* hptr) {
  uint32_t r[4];
  #pragma unroll
  for (int i = 0; i < 4; i++) {
    const int g = H * 4 + i;
    r[i] = mul_bf16x2(cvt_relu_bf16x2(acc[4 * g + 2 * R], acc[4 * g + 2 * R + 1]), cvt_bf16x2(acc[32 + 4 * g + 2 * R], acc[32 + 4 * g + 2 * R + 1]));
  }
  *reinterpret_cast<uint4*>(hptr + H * 1024 + R * 128) = make_uint4(r[0], r[1], r[2], r[3]);
}

struct ConsumerState {
  uint32_t bar;
  uint32_t descX, descW;
  uint32_t stage, phase;
  uint32_t prev_empty, db;
  bool elect, ready;
};

template<bool FIRST>
__device__ __forceinline__ void run_chunk(float (&acc)[64], const float (&prev)[64], ConsumerState& st, uint8_t* hprev, uint32_t hdone_prev, int lane) {
  #pragma unroll
  for (int kb = 0; kb < 9; kb++) {
    if (FIRST) mbar_wait(st.bar + B_XFULL + 8 * kb, 0);
    if (!st.ready) mbar_wait(st.bar + B_WFULL + 8 * st.stage, st.phase);
    const uint32_t da = st.descX + kb * (16384 >> 4);
    const uint32_t db = st.db;
    wgmma_fence();
    #pragma unroll
    for (int k = 0; k < 4; k++)
      wgmma2_n128<HI_SW128, HI_SW128, 0, 1>(acc, da + k * 2, db + k * (2048 >> 4), (kb == 0 && k == 0) ? 0 : 1);
    wgmma_commit();
    const uint32_t rel = st.prev_empty;
    st.prev_empty = st.bar + B_WEMPTY + 8 * st.stage;
    if (++st.stage == W_STAGES) { st.stage = 0; st.phase ^= 1; }
    st.db = st.descW + st.stage * (W_STAGE_BYTES >> 4);
    st.ready = mbar_test_wait(st.bar + B_WFULL + 8 * st.stage, st.phase);
    if (!(FIRST && kb == 0)) {
      wgmma_wait<1>();
      if (st.elect) mbar_arrive(rel);
    }
    if (!FIRST) {
      if (kb == 0) h_quarter<0, 0>(prev, hprev);
      if (kb == 1) h_quarter<0, 1>(prev, hprev);
      if (kb == 2) h_quarter<1, 0>(prev, hprev);
      if (kb == 3) {
        h_quarter<1, 1>(prev, hprev);
        __syncwarp();
        if (lane == 0) mbar_arrive(hdone_prev);
      }
    }
  }
}

template<int G0>
__device__ __forceinline__ void out_part(const float (&acc)[96], uint32_t stg, int lane, __nv_bfloat16* optr) {
  const uint32_t rowb = stg + (lane & 15) * 128;
  #pragma unroll
  for (int g = 0; g < 8; g += 2) {
    const int a = 4 * (G0 + g);
    uint32_t k0 = cvt_bf16x2(acc[a], acc[a + 1]), k1 = cvt_bf16x2(acc[a + 2], acc[a + 3]);
    uint32_t k2 = cvt_bf16x2(acc[a + 4], acc[a + 5]), k3 = cvt_bf16x2(acc[a + 6], acc[a + 7]);
    asm volatile("stmatrix.sync.aligned.m8n8.x4.shared.b16 [%0], {%1, %2, %3, %4};" :: "r"(rowb + (((g + (lane >> 4)) ^ (lane & 7)) << 4)), "r"(k0), "r"(k1), "r"(k2), "r"(k3) : "memory");
  }
  __syncwarp();
  #pragma unroll
  for (int i = 0; i < 4; i++) {
    const int r = i * 4 + (lane >> 3), c16 = lane & 7;
    uint4 v;
    asm volatile("ld.shared.v4.u32 {%0, %1, %2, %3}, [%4];" : "=r"(v.x), "=r"(v.y), "=r"(v.z), "=r"(v.w) : "r"(stg + r * 128 + ((c16 ^ (r & 7)) << 4)) : "memory");
    asm volatile("red.relaxed.gpu.global.add.noftz.v4.bf16x2 [%0], {%1, %2, %3, %4};" :: "l"(optr + (size_t)r * D_ + c16 * 8), "r"(v.x), "r"(v.y), "r"(v.z), "r"(v.w) : "memory");
  }
  __syncwarp();
}

__global__ void __launch_bounds__(384, 1)
ffn_kernel(const __grid_constant__ CUtensorMap tmX, const __grid_constant__ CUtensorMap tmWg, const __grid_constant__ CUtensorMap tmWu,
           const __grid_constant__ CUtensorMap tmWd, __nv_bfloat16* __restrict__ out) {
  extern __shared__ __align__(1024) uint8_t smem_raw[];
  const uint32_t sbase = (smem_u32(smem_raw) + 1023) & ~1023u;
  const uint32_t bar = sbase + OFF_BAR;
  const int tid = threadIdx.x, lane = tid & 31;
  const int warp = __shfl_sync(0xffffffffu, tid >> 5, 0), wg = warp >> 2;
  const int bid = blockIdx.x;
  const bool is_main = !(bid == 24 || bid == 25 || bid >= 130);
  const int rb = bid < 24 ? bid : bid - 2;
  const int j = ((rb >> 4) & 1) * 4 + ((rb >> 2) & 3), m = (rb >> 5) * 4 + (rb & 3);
  if (tid == 256) {
    prefetch_tmap(&tmX); prefetch_tmap(&tmWg); prefetch_tmap(&tmWu);
    for (int s = 0; s < W_STAGES; s++) { mbar_init(bar + B_WFULL + 8 * s, 1); mbar_init(bar + B_WEMPTY + 8 * s, 2); }
    for (int s = 0; s < 9; s++) { mbar_init(bar + B_XFULL + 8 * s, 1); mbar_init(bar + B_HDONE + 8 * s, 8); }
    for (int s = 0; s < P2_STAGES; s++) { mbar_init(bar + B_P2FULL + 8 * s, 1); mbar_init(bar + B_P2EMPTY + 8 * s, 2); }
    mbar_init(bar + B_EPOCH, 1); mbar_init(bar + B_ZDONE, 1); mbar_init(bar + B_TABLE, 1);
    asm volatile("fence.mbarrier_init.release.cluster;" ::: "memory");
    if (is_main) {
      mbar_expect_tx(bar + B_XFULL, 16384);
      tma_load_2d(sbase, &tmX, 0, m * 128, bar + B_XFULL);
      mbar_expect_tx(bar + B_WFULL, W_STAGE_BYTES);
      tma_load_2d(sbase + OFF_W, &tmWg, j * 576, 0, bar + B_WFULL);
      tma_load_2d(sbase + OFF_W + 8192, &tmWu, j * 576, 0, bar + B_WFULL);
    }
  }
  if (warp == 10) asm volatile("st.shared.u32 [%0], %1;" :: "r"(bar + B_READY + lane * 4), "r"(0) : "memory");
  __syncthreads();
  auto load_hdr = [&]() {
    uint4 h = __ldg(reinterpret_cast<const uint4*>(&g_sched[bid]));
    h.x = __shfl_sync(0xffffffffu, h.x, 0); h.y = __shfl_sync(0xffffffffu, h.y, 0);
    h.z = __shfl_sync(0xffffffffu, h.z, 0); h.w = __shfl_sync(0xffffffffu, h.w, 0);
    return h;
  };

  if (wg == 2) {
    reg_dealloc<40>();
    if (warp == 8) {
      if (lane == 0) {
        if (is_main) {
          uint32_t stage = 1, phase = 1;
          const int col0 = j * 576;
          for (int it = 1; it < 81; it++) {
            const int c = it / 9, kb = it - c * 9;
            if (it < 9) {
              mbar_expect_tx(bar + B_XFULL + 8 * it, 16384);
              tma_load_2d(sbase + it * 16384, &tmX, it * 64, m * 128, bar + B_XFULL + 8 * it);
            }
            mbar_wait(bar + B_WEMPTY + 8 * stage, phase);
            mbar_expect_tx(bar + B_WFULL + 8 * stage, W_STAGE_BYTES);
            const uint32_t dst = sbase + OFF_W + stage * W_STAGE_BYTES;
            tma_load_2d(dst, &tmWg, col0 + c * 64, kb * 64, bar + B_WFULL + 8 * stage);
            tma_load_2d(dst + 8192, &tmWu, col0 + c * 64, kb * 64, bar + B_WFULL + 8 * stage);
            if (++stage == W_STAGES) { stage = 0; phase ^= 1; }
          }
        }
        prefetch_tmap(&tmWd);
        mbar_wait(bar + B_TABLE, 0);
        uint4 hdr;
        asm volatile("ld.shared.v4.u32 {%0, %1, %2, %3}, [%4];" : "=r"(hdr.x), "=r"(hdr.y), "=r"(hdr.z), "=r"(hdr.w) : "r"(bar + B_SCHED) : "memory");
        const int nseg = (hdr.x >> 16) & 255;
        uint32_t s2 = 0, ph2 = 1;
        int n = 0;
        for (int sg = 0; sg < nseg; sg++) {
          const int sm = (hdr.y >> (8 * sg)) & 255, sn = (hdr.z >> (8 * sg)) & 255, cnt = (hdr.w >> (8 * sg)) & 255;
          const uint32_t rdy = bar + B_READY + (is_main ? 0 : sg * 32);
          const uint8_t* hsrc = g_h + (size_t)(sm * 72) * 16384;
          for (int js = 0; js < 8; js++) { uint32_t spin = 0; while (lds_acquire(rdy + js * 4) < 1) { __nanosleep(64); if (++spin > (1u << 24)) __trap(); } }
          for (int u = 0; u < cnt; u++, n++) {
            const int kb = lds_u8(bar + B_SCHED + 16 + n);
            const int js = kb / 9, c = kb - js * 9;
            { uint32_t spin = 0; while (lds_acquire(rdy + js * 4) <= (uint32_t)c) { __nanosleep(64); if (++spin > (1u << 24)) __trap(); } }
            if (n < P2_STAGES) {
              if (is_main && n > 0) {
                const int rel = (n == 1) ? 76 : 76 + n;
                mbar_wait(bar + B_WEMPTY + 8 * (rel % W_STAGES), (rel / W_STAGES) & 1);
              }
            } else {
              mbar_wait(bar + B_P2EMPTY + 8 * s2, ph2);
            }
            const uint32_t fb = bar + B_P2FULL + 8 * s2;
            mbar_expect_tx(fb, P2_STAGE_BYTES);
            const uint32_t dst = sbase + p2_slot(s2);
            bulk_load(dst, hsrc + (size_t)kb * 16384, P2_A_BYTES, fb);
            tma_load_5d(dst + P2_A_BYTES, &tmWd, kb * 32, sn * 3, fb);
            if (++s2 == P2_STAGES) { s2 = 0; ph2 ^= 1; }
          }
        }
      }
    } else if (warp == 9) {
      if (lane == 0) {
        const unsigned epoch = (unsigned)(atomicAdd(&g_count, 1ull) / NGRID);
        asm volatile("st.shared.u32 [%0], %1;" :: "r"(bar + B_EPOCH + 8), "r"(epoch) : "memory");
        mbar_arrive(bar + B_EPOCH);
        if (is_main) {
          mbar_wait(bar + B_ZDONE, 0);
          for (int c = 0; c < 9; c++) {
            if (c >= FLOAT_LEVELS && c < 5) continue;
            mbar_wait(bar + B_HDONE + 8 * c, 0);
            fence_proxy_async_global();
            st_release(&g_hflag[(m * 8 + j) * 32], epoch * 16 + c + 1);
          }
        }
      }
    } else if (warp == 10) {
      if (lane < 20) {
        const uint32_t w = __ldg(reinterpret_cast<const uint32_t*>(&g_sched[bid]) + lane);
        asm volatile("st.shared.u32 [%0], %1;" :: "r"(bar + B_SCHED + lane * 4), "r"(w) : "memory");
      }
      __syncwarp();
      if (lane == 0) mbar_arrive(bar + B_TABLE);
      const uint4 hdr = load_hdr();
      mbar_wait(bar + B_EPOCH, 0);
      unsigned epoch;
      asm volatile("ld.shared.u32 %0, [%1];" : "=r"(epoch) : "r"(bar + B_EPOCH + 8) : "memory");
      const int nseg = (hdr.x >> 16) & 255;
      const int wm = is_main ? m : (int)((hdr.y >> (8 * (lane >> 3))) & 255);
      const bool active = is_main ? lane < 8 : (lane >> 3) < nseg;
      const unsigned* fp = &g_hflag[(wm * 8 + (lane & 7)) * 32];
      const int want = is_main ? 9 : FLOAT_LEVELS;
      if (is_main) mbar_wait(bar + B_HDONE + 8 * 6, 0);
      int lvl = active ? 0 : 16;
      uint32_t n = 0;
      while (true) {
        if (lvl < want) {
          const int v = (int)(ld_acquire(fp) - epoch * 16);
          if (v > lvl) {
            fence_proxy_async_global();
            sts_release(bar + B_READY + lane * 4, (uint32_t)v);
            lvl = v;
          }
        }
        if (__all_sync(0xffffffffu, lvl >= want)) break;
        __nanosleep(200);
        if (++n > (1u << 22)) __trap();
      }
    } else if (is_main) {
      mbar_wait(bar + B_XFULL + 8 * 8, 0);
      uint4* ob = reinterpret_cast<uint4*>(out + (size_t)(m * 128 + j * 16) * D_);
      #pragma unroll 4
      for (int i = lane; i < 16 * 72; i += 32) ob[i] = make_uint4(0, 0, 0, 0);
      __syncwarp();
      if (lane == 0) mbar_arrive(bar + B_ZDONE);
    }
  } else {
    reg_alloc<232>();
    const int wq = warp & 3;
    const uint4 hdr = load_hdr();
    const int nseg = (hdr.x >> 16) & 255;
    ConsumerState st;
    st.bar = bar;
    st.descX = desc_lo(sbase + wg * 8192, 16);
    st.descW = desc_lo(sbase + OFF_W, 8192);
    st.stage = 0; st.phase = 0; st.prev_empty = 0; st.db = st.descW; st.ready = false;
    st.elect = (tid & 127) == 0;
    float acc[96];
    #pragma unroll
    for (int i = 0; i < 96; i++) acc[i] = 0.f;
    const uint32_t descA0 = desc_lo(sbase + wg * 8192, 1024);
    const uint32_t descB0 = desc_lo(sbase + P2_A_BYTES, 8192);
    uint32_t s2 = 0, ph2 = 0, off2 = 0;
    bool rdy2 = false;
    auto p2_step = [&](int scale_first, bool release_prev) {
      if (!rdy2) mbar_wait(bar + B_P2FULL + 8 * s2, ph2);
      const uint32_t da = descA0 + off2;
      const uint32_t db = descB0 + off2;
      wgmma_fence();
      #pragma unroll
      for (int k = 0; k < 4; k++)
        wgmma2_n192<HI_NOSW, HI_SW128, 0, 1>(acc, da + k * (2048 >> 4), db + k * (2048 >> 4), (k == 0) ? scale_first : 1);
      wgmma_commit();
      const uint32_t rel = st.prev_empty;
      st.prev_empty = bar + B_P2EMPTY + 8 * s2;
      if (++s2 == P2_STAGES) { s2 = 0; ph2 ^= 1; }
      off2 = p2_slot(s2) >> 4;
      rdy2 = mbar_test_wait(bar + B_P2FULL + 8 * s2, ph2);
      wgmma_wait<1>();
      if (st.elect && release_prev) mbar_arrive(rel);
    };
    #pragma unroll 1
    for (int sg = 0; sg < nseg; sg++) {
      const int sm = (hdr.y >> (8 * sg)) & 255, sn = (hdr.z >> (8 * sg)) & 255, cnt = (hdr.w >> (8 * sg)) & 255;
      if (sg == 0 && is_main) {
        uint8_t* hbase = g_h + ((size_t)(m * 72 + j * 9)) * 16384 + wg * 8192 + (lane & 3) * 2048 + wq * 256 + (lane >> 2) * 16;
        float accA[64], accB[64];
        run_chunk<true>(accA, accB, st, nullptr, 0, lane);
        if (tid == 0) { TS(g_ts, bid * 16 + 2); }
        #pragma unroll 1
        for (int cp = 0; cp < 4; cp++) {
          run_chunk<false>(accB, accA, st, hbase + (2 * cp) * 16384, bar + B_HDONE + 8 * (2 * cp), lane);
          run_chunk<false>(accA, accB, st, hbase + (2 * cp + 1) * 16384, bar + B_HDONE + 8 * (2 * cp + 1), lane);
        }
        if (tid == 0) { TS(g_ts, bid * 16 + 3); }
        p2_step(0, true);
        h_quarter<0, 0>(accA, hbase + 8 * 16384);
        h_quarter<0, 1>(accA, hbase + 8 * 16384);
        h_quarter<1, 0>(accA, hbase + 8 * 16384);
        h_quarter<1, 1>(accA, hbase + 8 * 16384);
        __syncwarp();
        if (lane == 0) mbar_arrive(bar + B_HDONE + 8 * 8);
      } else {
        p2_step(0, false);
      }
      const int hold = (sg == nseg - 1 && cnt > SKEW) ? cnt - SKEW : cnt;
      #pragma unroll 1
      for (int i = 1; i < cnt; i++) {
        if (wg == 1 && i == hold) asm volatile("bar.sync 1, 256;" ::: "memory");
        p2_step(1, true);
      }
      if (wg == 0 && hold < cnt) asm volatile("bar.arrive 1, 256;" ::: "memory");
      wgmma_wait<0>();
      if (st.elect) mbar_arrive(st.prev_empty);
      if (tid == 0 && sg == nseg - 1) { TS(g_ts, bid * 16 + 4); }
      const uint32_t stg = sbase + OFF_STG + warp * 2048;
      __nv_bfloat16* optr = out + (size_t)(sm * 128 + wg * 64 + wq * 16) * D_ + sn * 192;
      out_part<0>(acc, stg, lane, optr);
      out_part<8>(acc, stg, lane, optr + 64);
      out_part<16>(acc, stg, lane, optr + 128);
    }
  }
}

__global__ void fb_h_kernel(const __nv_bfloat16* __restrict__ x, const __nv_bfloat16* __restrict__ wg, const __nv_bfloat16* __restrict__ wu) {
  const int f = blockIdx.x * blockDim.x + threadIdx.x, s = blockIdx.y;
  float g = 0.f, u = 0.f;
  for (int d = 0; d < D_; d++) {
    const float xv = __bfloat162float(x[s * D_ + d]);
    g = fmaf(xv, __bfloat162float(wg[(size_t)d * F_ + f]), g);
    u = fmaf(xv, __bfloat162float(wu[(size_t)d * F_ + f]), u);
  }
  const float gb = fmaxf(__bfloat162float(__float2bfloat16(g)), 0.f), ub = __bfloat162float(__float2bfloat16(u));
  reinterpret_cast<__nv_bfloat16*>(g_h)[(size_t)s * F_ + f] = __float2bfloat16(gb * ub);
}
__global__ void fb_out_kernel(const __nv_bfloat16* __restrict__ wd, __nv_bfloat16* __restrict__ out) {
  const int d = blockIdx.x * blockDim.x + threadIdx.x, s = blockIdx.y;
  const __nv_bfloat16* h = reinterpret_cast<const __nv_bfloat16*>(g_h) + (size_t)s * F_;
  float a = 0.f;
  for (int f = 0; f < F_; f++) a = fmaf(__bfloat162float(h[f]), __bfloat162float(wd[(size_t)f * D_ + d]), a);
  out[(size_t)s * D_ + d] = __float2bfloat16(a);
}

typedef CUresult (*PFN_encodeTiled)(CUtensorMap*, CUtensorMapDataType, cuuint32_t, void*, const cuuint64_t*, const cuuint64_t*, const cuuint32_t*, const cuuint32_t*, CUtensorMapInterleave, CUtensorMapSwizzle, CUtensorMapL2promotion, CUtensorMapFloatOOBfill);

CUtensorMap make_tmap(PFN_encodeTiled fn, const void* ptr, uint64_t rows, uint64_t cols, uint32_t box_rows, uint32_t box_cols) {
  CUtensorMap m;
  cuuint64_t gd[2] = {cols, rows};
  cuuint64_t gs[1] = {cols * 2};
  cuuint32_t bd[2] = {box_cols, box_rows};
  cuuint32_t es[2] = {1, 1};
  fn(&m, CU_TENSOR_MAP_DATA_TYPE_BFLOAT16, 2, const_cast<void*>(ptr), gd, gs, bd, es, CU_TENSOR_MAP_INTERLEAVE_NONE, CU_TENSOR_MAP_SWIZZLE_128B,
     CU_TENSOR_MAP_L2_PROMOTION_L2_128B, CU_TENSOR_MAP_FLOAT_OOB_FILL_NONE);
  return m;
}

}

extern "C" void kernel_launch(void* const* d_in, const int* in_sizes, int n_in, void* d_out, int out_size) {
  static PFN_encodeTiled enc = nullptr;
  static bool setup_done = false, fast = false;
  if (!setup_done) {
    void* p = nullptr; cudaDriverEntryPointQueryResult qr;
    cudaGetDriverEntryPoint("cuTensorMapEncodeTiled", &p, cudaEnableDefault, &qr);
    enc = (PFN_encodeTiled)p;
    int dev = 0, sms = 0, occ = 0;
    cudaGetDevice(&dev);
    cudaDeviceGetAttribute(&sms, cudaDevAttrMultiProcessorCount, dev);
    const bool attr_ok = cudaFuncSetAttribute(ffn_kernel, cudaFuncAttributeMaxDynamicSharedMemorySize, SMEM_BYTES) == cudaSuccess;
    if (attr_ok) cudaOccupancyMaxActiveBlocksPerMultiprocessor(&occ, ffn_kernel, 384, SMEM_BYTES);
    fast = enc != nullptr && attr_ok && occ * sms >= NGRID;
    (void)cudaGetLastError();
    setup_done = true;
  }
  if (!fast) {
    fb_h_kernel<<<dim3(F_ / 128, S_), 128, 0, cudaStreamPerThread>>>((const __nv_bfloat16*)d_in[0], (const __nv_bfloat16*)d_in[1], (const __nv_bfloat16*)d_in[2]);
    fb_out_kernel<<<dim3(D_ / 64, S_), 64, 0, cudaStreamPerThread>>>((const __nv_bfloat16*)d_in[3], (__nv_bfloat16*)d_out);
    return;
  }
  CUtensorMap tmX = make_tmap(enc, d_in[0], S_, D_, 128, 64);
  CUtensorMap tmWg = make_tmap(enc, d_in[1], D_, F_, 64, 64);
  CUtensorMap tmWu = make_tmap(enc, d_in[2], D_, F_, 64, 64);
  CUtensorMap tmWd;
  {
    cuuint64_t gd[5] = {64, 2, 8, 72 * 32, 9};
    cuuint64_t gs[4] = {(cuuint64_t)D_ * 2, (cuuint64_t)D_ * 2 * 8, (cuuint64_t)D_ * 2 * 2, 128};
    cuuint32_t bd[5] = {64, 2, 8, 4, 3};
    cuuint32_t es[5] = {1, 1, 1, 1, 1};
    enc(&tmWd, CU_TENSOR_MAP_DATA_TYPE_BFLOAT16, 5, d_in[3], gd, gs, bd, es, CU_TENSOR_MAP_INTERLEAVE_NONE, CU_TENSOR_MAP_SWIZZLE_128B,
        CU_TENSOR_MAP_L2_PROMOTION_L2_128B, CU_TENSOR_MAP_FLOAT_OOB_FILL_NONE);
  }
  ffn_kernel<<<NGRID, 384, SMEM_BYTES, cudaStreamPerThread>>>(tmX, tmWg, tmWu, tmWd, (__nv_bfloat16*)d_out);
}
```
